```python
import torch

def _softmax(x, axis=-1):
    return torch.softmax(x, dim=axis)
def _gelu(x):
    return torch.nn.functional.gelu(x, approximate="tanh")
def _silu(x):
    return torch.nn.functional.silu(x)
def _sigmoid(x):
    return torch.sigmoid(x)
def _layernorm(x, axis=-1, eps=1e-5):
    m = x.mean(dim=axis, keepdim=True)
    v = x.var(dim=axis, keepdim=True, unbiased=False)
    return (x - m) / torch.sqrt(v + eps)
def _scatter_add(tgt, idx, src, axis=0):
    return tgt.clone().index_add_(axis, idx, src)
def _segment_sum(src, seg, n):
    out = torch.zeros((n,) + src.shape[1:], dtype=src.dtype)
    return out.index_add_(0, seg, src)
def _pad(x, pw):
    flat = tuple(v for pair in reversed(pw) for v in pair)
    return torch.nn.functional.pad(x, flat)

kernel_name = 'recurrent_scan__mha_block_cached__geglu_ffn__decode'

def setup_inputs():

    _w = (lambda a: (lambda t: t.to(torch.bfloat16) if t.is_floating_point() else t)(torch.as_tensor(a)))
    def _A_setup():
        B, Sq, D = 2, 1, 512
        H, Sk, Dh = 32, 8192, 128
        return {
            "x": _w((lambda *s: torch.randn(*s, dtype=torch.bfloat16) * 0.05)(B, Sq, D)),
            "k_cache": _w((lambda *s: torch.randn(*s, dtype=torch.bfloat16) * 1.6)(B, H, Sk, Dh)),
            "v_cache": _w((lambda *s: torch.randn(*s, dtype=torch.bfloat16) * 0.2)(B, H, Sk, Dh)),
            "wq": _w((lambda *s: torch.randn(*s, dtype=torch.bfloat16) * 1.6)(D, H * Dh) * (D ** -0.5)),
            "wo": _w((lambda *s: torch.randn(*s, dtype=torch.bfloat16) * 0.2)(H * Dh, D) * ((H * Dh) ** -0.5)),
        }
    _A_in = _A_setup()

    def _B_setup():
        B, S, D, F = 2, 1, 512, 1376
        return {
            "x": _w((lambda *s: torch.randn(*s, dtype=torch.bfloat16) * 0.05)(B, S, D)),
            "w_gate": _w((lambda *s: torch.randn(*s, dtype=torch.bfloat16) * 0.1)(D, F)),
            "w_up": _w((lambda *s: torch.randn(*s, dtype=torch.bfloat16) * 0.1)(D, F)),
            "w_down": _w((lambda *s: torch.randn(*s, dtype=torch.bfloat16) * 0.1)(F, D)),
        }
    _B_in = _B_setup()

    return {
        "A_x": _A_in["x"],
        "A_k_cache": _A_in["k_cache"],
        "A_v_cache": _A_in["v_cache"],
        "A_wq": _A_in["wq"],
        "A_wo": _A_in["wo"],
        "B_x": _B_in["x"],
        "B_w_gate": _B_in["w_gate"],
        "B_w_up": _B_in["w_up"],
        "B_w_down": _B_in["w_down"],
    }

def reference(A_x, A_k_cache, A_v_cache, A_wq, A_wo, B_x, B_w_gate, B_w_up, B_w_down):
    def _A_ref(x, k_cache, v_cache, wq, wo):
        B, Sq, D = x.shape
        H, Dh = 32, 128
        q = (lambda x, *d: x.permute(*d))((x @ wq).reshape(B, Sq, H, Dh), 0, 2, 1, 3)
        scores = torch.einsum("bhqd,bhkd->bhqk", q, k_cache) * (Dh ** -0.5)
        p = _softmax(scores, axis=-1)
        o = torch.einsum("bhqk,bhkd->bhqd", p, v_cache)
        return (lambda x, *d: x.permute(*d))(o, 0, 2, 1, 3).reshape(B, Sq, H * Dh) @ wo

    def _B_ref(x, w_gate, w_up, w_down):
        return (_gelu(x @ w_gate) * (x @ w_up)) @ w_down

    x = A_x
    xn = _layernorm(x, axis=-1)
    s = _A_ref(xn, A_k_cache, A_v_cache, A_wq, A_wo)
    g = _silu(_B_ref(xn, B_w_gate, B_w_up, B_w_down))
    return x + s * g
```

```cpp
#include <cuda_runtime.h>
#include <cuda_bf16.h>
#include <stdint.h>

namespace {

constexpr int DM = 512, NH = 32, SK = 8192, DH = 128, FF = 1376;
constexpr int NBH = 2 * NH;
constexpr int TILE_KEYS = 128;
constexpr int TILE_BYTES = TILE_KEYS * DH * 2;
constexpr int TPB = SK / TILE_KEYS;
constexpr int NITEMS = NBH * TPB;
#define NSLOTS 6
constexpr int NPRE = NSLOTS / 2;
constexpr int NCONS = 256, NAUX = 128, NTHREADS = NCONS + NAUX + 32;
constexpr int NROLE = 128;
constexpr int NFFN = FF / 16;
constexpr int PUNITS = 12;
constexpr float LOG2E = 1.4426950408889634f;
constexpr unsigned SPIN_LIMIT = 1u << 22;

__device__ unsigned long long g_start;
__device__ unsigned int g_ticket[2];
__device__ uint4 g_q[NBH * 32];
__device__ uint4 g_part[NBH * 4 * TPB * PUNITS];
__device__ uint4 g_f[NROLE * NFFN * 4];
__device__ uint4 g_y[NROLE * NROLE * 4];
#define PROF(i) do {} while (0)

struct __align__(128) Smem {
    unsigned char ring[NSLOTS * TILE_BYTES];
    uint32_t qs[NPRE][64];
    float red_o[2][8][128];
    float red_l[2][64];
    float red_m[2][8];
    float stage[2][4 * 36];
    float comb[TPB * 36];
    float comb2[4][36];
    float2 xn[DM];
    float redp[8][64];
    float hs[2][16];
    float2 so[32];
    float fred[8][8];
    float sg[8];
    unsigned long long full[NSLOTS], empty[NSLOTS], o_ready;
    int info[NPRE];
    volatile int progress;
    volatile uint32_t tag;
};

__device__ __forceinline__ uint32_t smem_u32(const void* p) { return (uint32_t)__cvta_generic_to_shared(p); }
__device__ __forceinline__ void mbar_init(uint32_t bar, uint32_t cnt) {
    asm volatile("mbarrier.init.shared::cta.b64 [%0], %1;" ::"r"(bar), "r"(cnt) : "memory");
}
__device__ __forceinline__ void mbar_expect_tx(uint32_t bar, uint32_t bytes) {
    asm volatile("mbarrier.arrive.expect_tx.shared::cta.b64 _, [%0], %1;" ::"r"(bar), "r"(bytes) : "memory");
}
__device__ __forceinline__ void mbar_arrive(uint32_t bar) {
    asm volatile("mbarrier.arrive.shared::cta.b64 _, [%0];" ::"r"(bar) : "memory");
}
__device__ __forceinline__ void mbar_wait(uint32_t bar, uint32_t parity) {
    uint32_t ok, n = 0;
    do {
        asm volatile("{\n.reg .pred p;\nmbarrier.try_wait.parity.shared::cta.b64 p, [%1], %2;\nselp.u32 %0, 1, 0, p;\n}"
                     : "=r"(ok) : "r"(bar), "r"(parity) : "memory");
        if (++n > SPIN_LIMIT) __trap();
    } while (!ok);
}
__device__ __forceinline__ void bulk_load(uint32_t dst, const void* src, uint32_t bytes, uint32_t bar, uint64_t pol) {
    asm volatile("cp.async.bulk.shared::cluster.global.mbarrier::complete_tx::bytes.L2::cache_hint [%0], [%1], %2, [%3], %4;"
                 ::"r"(dst), "l"(src), "r"(bytes), "r"(bar), "l"(pol) : "memory");
}
__device__ __forceinline__ void bar_sync(int id, int n) { asm volatile("bar.sync %0, %1;" ::"r"(id), "r"(n) : "memory"); }
__device__ __forceinline__ void bar_arrive(int id, int n) { asm volatile("bar.arrive %0, %1;" ::"r"(id), "r"(n) : "memory"); }
__device__ __forceinline__ uint4 ldg_nc(const void* p) {
    uint4 v;
    asm volatile("ld.global.nc.L1::no_allocate.v4.u32 {%0,%1,%2,%3}, [%4];" : "=r"(v.x), "=r"(v.y), "=r"(v.z), "=r"(v.w) : "l"(p));
    return v;
}
__device__ __forceinline__ uint32_t ldg_nc32(const void* p) {
    uint32_t v;
    asm volatile("ld.global.nc.L1::no_allocate.u32 %0, [%1];" : "=r"(v) : "l"(p));
    return v;
}
__device__ __forceinline__ void st_ll64x2(uint4* p, uint32_t a, uint32_t b, uint32_t tag) {
    asm volatile("{\n.reg .b64 x, y;\nmov.b64 x, {%1, %3};\nmov.b64 y, {%2, %3};\nst.relaxed.gpu.global.v2.b64 [%0], {x, y};\n}"
                 ::"l"(p), "r"(a), "r"(b), "r"(tag) : "memory");
}
__device__ __forceinline__ void st_ll64(void* p, uint32_t a, uint32_t tag) {
    asm volatile("{\n.reg .b64 x;\nmov.b64 x, {%1, %2};\nst.relaxed.gpu.global.b64 [%0], x;\n}" ::"l"(p), "r"(a), "r"(tag) : "memory");
}
__device__ __forceinline__ uint4 ld_ll64x2(const uint4* p) {
    uint4 v;
    asm volatile("{\n.reg .b64 x, y;\nld.relaxed.gpu.global.v2.b64 {x, y}, [%4];\nmov.b64 {%0, %1}, x;\nmov.b64 {%2, %3}, y;\n}"
                 : "=r"(v.x), "=r"(v.y), "=r"(v.z), "=r"(v.w) : "l"(p) : "memory");
    return v;
}
__device__ __forceinline__ void st_ll128(uint4* p, uint32_t a, uint32_t b, uint32_t c, uint32_t tag) {
    asm volatile("{\n.reg .b64 x, y;\n.reg .b128 z;\nmov.b64 x, {%1, %2};\nmov.b64 y, {%3, %4};\nmov.b128 z, {x, y};\n"
                 "st.relaxed.gpu.global.b128 [%0], z;\n}" ::"l"(p), "r"(a), "r"(b), "r"(c), "r"(tag) : "memory");
}
__device__ __forceinline__ uint4 ld_ll128(const uint4* p) {
    uint4 v;
    asm volatile("{\n.reg .b64 x, y;\n.reg .b128 z;\nld.relaxed.gpu.global.b128 z, [%4];\nmov.b128 {x, y}, z;\n"
                 "mov.b64 {%0, %1}, x;\nmov.b64 {%2, %3}, y;\n}"
                 : "=r"(v.x), "=r"(v.y), "=r"(v.z), "=r"(v.w) : "l"(p) : "memory");
    return v;
}
__device__ __forceinline__ void ldsm_x4(uint32_t addr, uint32_t& a0, uint32_t& a1, uint32_t& a2, uint32_t& a3) {
    asm volatile("ldmatrix.sync.aligned.m8n8.x4.shared.b16 {%0,%1,%2,%3}, [%4];"
                 : "=r"(a0), "=r"(a1), "=r"(a2), "=r"(a3) : "r"(addr) : "memory");
}
__device__ __forceinline__ void ldsm_x4_t(uint32_t addr, uint32_t& a0, uint32_t& a1, uint32_t& a2, uint32_t& a3) {
    asm volatile("ldmatrix.sync.aligned.m8n8.x4.trans.shared.b16 {%0,%1,%2,%3}, [%4];"
                 : "=r"(a0), "=r"(a1), "=r"(a2), "=r"(a3) : "r"(addr) : "memory");
}
__device__ __forceinline__ void mma_bf16(float* d, uint32_t a0, uint32_t a1, uint32_t a2, uint32_t a3, uint32_t b0, uint32_t b1) {
    asm volatile("mma.sync.aligned.m16n8k16.row.col.f32.bf16.bf16.f32 {%0,%1,%2,%3}, {%4,%5,%6,%7}, {%8,%9}, {%0,%1,%2,%3};"
                 : "+f"(d[0]), "+f"(d[1]), "+f"(d[2]), "+f"(d[3]) : "r"(a0), "r"(a1), "r"(a2), "r"(a3), "r"(b0), "r"(b1));
}
__device__ __forceinline__ float bf_lo(uint32_t w) { return __uint_as_float(w << 16); }
__device__ __forceinline__ float bf_hi(uint32_t w) { return __uint_as_float(w & 0xffff0000u); }
__device__ __forceinline__ float rbf(float x) { return __bfloat162float(__float2bfloat16_rn(x)); }
__device__ __forceinline__ uint32_t bf_bits(float x) { return (uint32_t)__bfloat16_as_ushort(__float2bfloat16_rn(x)); }
__device__ __forceinline__ float ex2(float x) { float y; asm("ex2.approx.ftz.f32 %0, %1;" : "=f"(y) : "f"(x)); return y; }
__device__ __forceinline__ int f2ord(float f) { int i = __float_as_int(f); return i ^ ((i >> 31) & 0x7fffffff); }
__device__ __forceinline__ float ord2f(int i) { return __int_as_float(i ^ ((i >> 31) & 0x7fffffff)); }
__device__ __forceinline__ float warp_max(float v) { return ord2f(__reduce_max_sync(0xffffffffu, f2ord(v))); }

template <int N>
__device__ __forceinline__ void xreduce(float* v, int mask, bool upper) {
#pragma unroll
    for (int i = 0; i < N; i++) {
        float keep = upper ? v[N + i] : v[i];
        float send = upper ? v[i] : v[N + i];
        v[i] = keep + __shfl_xor_sync(0xffffffffu, send, mask);
    }
}
__device__ __forceinline__ void fma8(float* acc0, float* acc1, const uint4& w, float2 x) {
    const uint32_t ww[4] = {w.x, w.y, w.z, w.w};
#pragma unroll
    for (int j = 0; j < 4; j++) {
        float lo = bf_lo(ww[j]), hi = bf_hi(ww[j]);
        acc0[2 * j] = fmaf(x.x, lo, acc0[2 * j]);
        acc0[2 * j + 1] = fmaf(x.x, hi, acc0[2 * j + 1]);
        acc1[2 * j] = fmaf(x.y, lo, acc1[2 * j]);
        acc1[2 * j + 1] = fmaf(x.y, hi, acc1[2 * j + 1]);
    }
}

enum { BAR_CONS = 1, BAR_AUX = 2, BAR_TAG = 3 };

__global__ void __launch_bounds__(NTHREADS, 1)
fused_decode_kernel(const __nv_bfloat16* __restrict__ x, const __nv_bfloat16* __restrict__ kc,
                    const __nv_bfloat16* __restrict__ vc, const __nv_bfloat16* __restrict__ wq,
                    const __nv_bfloat16* __restrict__ wo, const __nv_bfloat16* __restrict__ wg,
                    const __nv_bfloat16* __restrict__ wu, const __nv_bfloat16* __restrict__ wd,
                    __nv_bfloat16* __restrict__ out) {
    extern __shared__ __align__(1024) unsigned char smem_raw[];
    Smem& sm = *reinterpret_cast<Smem*>(smem_raw);
    const int tid = threadIdx.x, lane = tid & 31, warp = tid >> 5;
    const int cta = blockIdx.x, G = gridDim.x;
    const bool role = cta < NROLE;
    const uint32_t ring = smem_u32(sm.ring);
    const uint32_t full0 = smem_u32(&sm.full[0]), empty0 = smem_u32(&sm.empty[0]);

    if (warp < 8) {
        if (tid == 0) PROF(0);
        const int fc = cta - (G - NFFN);
        const int bw = warp >> 2;
        const uint4 xa = *reinterpret_cast<const uint4*>(x + bw * DM + lane * 16);
        const uint4 xb = *reinterpret_cast<const uint4*>(x + bw * DM + lane * 16 + 8);
        const uint2 xo = *reinterpret_cast<const uint2*>(x + tid * 4);
        uint4 rq[8], rg[4], ru[4];
        uint32_t rd[16];
        if (role) {
#pragma unroll
            for (int i = 0; i < 8; i++) rq[i] = ldg_nc(wq + (size_t)((tid >> 2) + 64 * i) * (NH * DH) + cta * 32 + (tid & 3) * 8);
        }
        if (fc >= 0) {
#pragma unroll
            for (int i = 0; i < 4; i++) {
                const size_t off = (size_t)((tid >> 1) + 128 * i) * FF + fc * 16 + (tid & 1) * 8;
                rg[i] = ldg_nc(wg + off);
                ru[i] = ldg_nc(wu + off);
            }
#pragma unroll
            for (int r = 0; r < 16; r++) rd[r] = ldg_nc32(wd + (size_t)(fc * 16 + r) * DM + tid * 2);
        }
        float xfin = 0.f;
        if (role && tid < 8) xfin = __bfloat162float(x[cta * 8 + tid]);
        __syncthreads();

        {
            const uint32_t xw[8] = {xa.x, xa.y, xa.z, xa.w, xb.x, xb.y, xb.z, xb.w};
            float s = 0.f;
#pragma unroll
            for (int j = 0; j < 8; j++) s += bf_lo(xw[j]) + bf_hi(xw[j]);
#pragma unroll
            for (int o = 16; o; o >>= 1) s += __shfl_xor_sync(0xffffffffu, s, o);
            const float mean = s * (1.0f / DM);
            float v = 0.f;
#pragma unroll
            for (int j = 0; j < 8; j++) {
                float a = bf_lo(xw[j]) - mean, b = bf_hi(xw[j]) - mean;
                v = fmaf(a, a, v);
                v = fmaf(b, b, v);
            }
#pragma unroll
            for (int o = 16; o; o >>= 1) v += __shfl_xor_sync(0xffffffffu, v, o);
            const float mb = rbf(mean);
            const float den = rbf(__fsqrt_rn(rbf(rbf(v * (1.0f / DM)) + 1e-5f)));
            float* xnf = reinterpret_cast<float*>(sm.xn);
            const int e = (tid & 127) * 4;
            xnf[(e + 0) * 2 + bw] = rbf(__fdiv_rn(rbf(bf_lo(xo.x) - mb), den));
            xnf[(e + 1) * 2 + bw] = rbf(__fdiv_rn(rbf(bf_hi(xo.x) - mb), den));
            xnf[(e + 2) * 2 + bw] = rbf(__fdiv_rn(rbf(bf_lo(xo.y) - mb), den));
            xnf[(e + 3) * 2 + bw] = rbf(__fdiv_rn(rbf(bf_hi(xo.y) - mb), den));
        }
        bar_sync(BAR_CONS, NCONS);

        if (role) {
            float acc[16];
#pragma unroll
            for (int j = 0; j < 16; j++) acc[j] = 0.f;
#pragma unroll
            for (int i = 0; i < 8; i++) fma8(acc, acc + 8, rq[i], sm.xn[(tid >> 2) + 64 * i]);
            xreduce<8>(acc, 16, lane & 16);
            xreduce<4>(acc, 8, lane & 8);
            xreduce<2>(acc, 4, lane & 4);
            const int pos = ((lane >> 4) & 1) * 32 + (lane & 3) * 8 + ((lane >> 3) & 1) * 4 + ((lane >> 2) & 1) * 2;
            *reinterpret_cast<float2*>(&sm.redp[warp][pos]) = make_float2(acc[0], acc[1]);
        }
        bar_sync(BAR_TAG, NCONS + 32);
        const uint32_t tag = sm.tag;
        if (role && warp == 0) {
            float a = 0.f, b = 0.f;
#pragma unroll
            for (int w = 0; w < 8; w++) {
                float2 t = *reinterpret_cast<const float2*>(&sm.redp[w][lane * 2]);
                a += t.x;
                b += t.y;
            }
            const int bh = (lane >> 4) * NH + (cta >> 2);
            st_ll64(reinterpret_cast<unsigned long long*>(g_q) + bh * 64 + (cta & 3) * 16 + (lane & 15),
                    bf_bits(a) | (bf_bits(b) << 16), tag);
        }
        if (tid == 0) PROF(1);

        if (fc >= 0) {
            float acc[32];
#pragma unroll
            for (int j = 0; j < 32; j++) acc[j] = 0.f;
#pragma unroll
            for (int i = 0; i < 4; i++) {
                const float2 xv = sm.xn[(tid >> 1) + 128 * i];
                fma8(acc, acc + 8, rg[i], xv);
                fma8(acc + 16, acc + 24, ru[i], xv);
            }
            xreduce<16>(acc, 16, lane & 16);
            xreduce<8>(acc, 8, lane & 8);
            xreduce<4>(acc, 4, lane & 4);
            xreduce<2>(acc, 2, lane & 2);
            bar_sync(BAR_CONS, NCONS);
            const int pos = ((lane >> 4) & 1) * 32 + ((lane >> 3) & 1) * 16 + (lane & 1) * 8 + ((lane >> 2) & 1) * 4 + ((lane >> 1) & 1) * 2;
            *reinterpret_cast<float2*>(&sm.redp[warp][pos]) = make_float2(acc[0], acc[1]);
            bar_sync(BAR_CONS, NCONS);
            if (warp == 0) {
                float g = 0.f, u = 0.f;
#pragma unroll
                for (int w = 0; w < 8; w++) {
                    g += sm.redp[w][lane];
                    u += sm.redp[w][32 + lane];
                }
                g = rbf(g);
                u = rbf(u);
                const float inner = 0.7978845608028654f * (g + 0.044715f * g * g * g);
                const float ge = rbf(0.5f * g * (1.0f + tanhf(inner)));
                sm.hs[lane >> 4][lane & 15] = rbf(ge * u);
            }
            bar_sync(BAR_CONS, NCONS);
            float f00 = 0.f, f01 = 0.f, f10 = 0.f, f11 = 0.f;
#pragma unroll
            for (int r = 0; r < 16; r++) {
                const float lo = bf_lo(rd[r]), hi = bf_hi(rd[r]);
                const float h0 = sm.hs[0][r], h1 = sm.hs[1][r];
                f00 = fmaf(h0, lo, f00);
                f01 = fmaf(h0, hi, f01);
                f10 = fmaf(h1, lo, f10);
                f11 = fmaf(h1, hi, f11);
            }
            st_ll64x2(&g_f[((tid >> 2) * NFFN + fc) * 4 + (tid & 3)], __float_as_uint(f00), __float_as_uint(f01), tag);
            st_ll64x2(&g_f[((64 + (tid >> 2)) * NFFN + fc) * 4 + (tid & 3)], __float_as_uint(f10), __float_as_uint(f11), tag);
        }
        if (tid == 0) PROF(2);

        const int g = lane >> 2, q4 = lane & 3;
        const bool diag = (q4 == (g >> 1));
        const int lr = lane & 7, lm = lane >> 3;
        const uint32_t k_row = (uint32_t)((warp * 16 + (lm & 1) * 8 + lr) * 256 + (lm >> 1) * 128);
        const uint32_t v_row = (uint32_t)((warp * 16 + (lm >> 1) * 8 + lr) * 256 + (lm & 1) * 128);
        int pi = 0;
        uint32_t ph = 0;
        int it = 0;
        for (;; ++it) {
            const uint32_t kslot = ring + (2 * pi) * TILE_BYTES, vslot = kslot + TILE_BYTES;
            mbar_wait(full0 + (2 * pi) * 8, ph);
            const int item = *reinterpret_cast<volatile int*>(&sm.info[pi]);
            if (item < 0) break;
            if (it == 0 && tid == 0) PROF(3);
            float sa[4] = {0.f, 0.f, 0.f, 0.f}, sb[4] = {0.f, 0.f, 0.f, 0.f};
#pragma unroll
            for (int s = 0; s < 8; s++) {
                uint32_t a0, a1, a2, a3;
                ldsm_x4(kslot + k_row + (((s + lr) & 7) << 4), a0, a1, a2, a3);
                const int j = ((s + g) & 7) * 4 + q4;
                mma_bf16((s & 1) ? sb : sa, a0, a1, a2, a3, sm.qs[pi][j], sm.qs[pi][32 + j]);
            }
            __syncwarp();
            if (lane == 0) mbar_arrive(empty0 + (2 * pi) * 8);
            float s0 = (g & 1) ? sa[1] + sb[1] : sa[0] + sb[0];
            float s1 = (g & 1) ? sa[3] + sb[3] : sa[2] + sb[2];
            s0 = rbf(rbf(s0) * 0.08838834764831845f) * LOG2E;
            s1 = rbf(rbf(s1) * 0.08838834764831845f) * LOG2E;
            const float m = fmaxf(warp_max(diag ? fmaxf(s0, s1) : -INFINITY), -3.0e38f);
            const uint32_t p0 = diag ? bf_bits(ex2(s0 - m)) : 0u;
            const uint32_t p1 = diag ? bf_bits(ex2(s1 - m)) : 0u;
            const uint32_t b0 = (g & 1) ? (p0 << 16) : p0;
            const uint32_t b1 = (g & 1) ? (p1 << 16) : p1;
            const int rb = it & 1;
            if (diag) sm.red_l[rb][warp * 8 + g] = __uint_as_float(p0 << 16) + __uint_as_float(p1 << 16);
            if (lane == 0) sm.red_m[rb][warp] = m;
            mbar_wait(full0 + (2 * pi + 1) * 8, ph);
            float d[8][4];
#pragma unroll
            for (int c = 0; c < 8; c++) {
                uint32_t a0, a1, a2, a3;
                ldsm_x4_t(vslot + v_row + (((c + lr) & 7) << 4), a0, a1, a2, a3);
                d[c][0] = d[c][1] = d[c][2] = d[c][3] = 0.f;
                mma_bf16(d[c], a0, a1, a2, a3, b0, b1);
            }
            __syncwarp();
            if (lane == 0) mbar_arrive(empty0 + (2 * pi + 1) * 8);
            float e[8], f[8];
#pragma unroll
            for (int c = 0; c < 8; c++) {
                e[c] = d[c][0] + d[(c + 7) & 7][1];
                f[c] = d[c][2] + d[(c + 7) & 7][3];
            }
#pragma unroll
            for (int c = 0; c < 4; c++) {
                e[c] += __shfl_xor_sync(0xffffffffu, e[c + 4], 2);
                f[c] += __shfl_xor_sync(0xffffffffu, f[c + 4], 2);
            }
            const int src = (lane & ~3) | ((q4 + 3) & 3);
#pragma unroll
            for (int c = 0; c < 2; c++) {
                e[c] += __shfl_sync(0xffffffffu, e[c + 2], src);
                f[c] += __shfl_sync(0xffffffffu, f[c + 2], src);
            }
            *reinterpret_cast<float4*>(&sm.red_o[rb][warp][lane * 4]) = make_float4(e[0], e[1], f[0], f[1]);
            bar_sync(BAR_CONS, NCONS);
            if (warp == (it & 7)) {
                const float mw = sm.red_m[rb][lane & 7];
                const float M = warp_max(mw);
                const float sc = ex2(mw - M);
                float4 o = make_float4(0.f, 0.f, 0.f, 0.f);
#pragma unroll
                for (int w = 0; w < 8; w++) {
                    const float4 t = *reinterpret_cast<const float4*>(&sm.red_o[rb][w][lane * 4]);
                    const float s = __shfl_sync(0xffffffffu, sc, w);
                    o.x = fmaf(s, t.x, o.x);
                    o.y = fmaf(s, t.y, o.y);
                    o.z = fmaf(s, t.z, o.z);
                    o.w = fmaf(s, t.w, o.w);
                }
                const float2 lv = *reinterpret_cast<const float2*>(&sm.red_l[rb][lane * 2]);
                float L = (lv.x + lv.y) * __shfl_sync(0xffffffffu, sc, lane >> 2);
#pragma unroll
                for (int of = 16; of; of >>= 1) L += __shfl_xor_sync(0xffffffffu, L, of);
                float* st = sm.stage[rb];
                const int sl = q4 >> 1, ps = (q4 & 1) * 16 + g;
                st[sl * 36 + ps] = o.x;
                st[sl * 36 + ps + 8] = o.y;
                st[(sl + 2) * 36 + ps] = o.z;
                st[(sl + 2) * 36 + ps + 8] = o.w;
                if (lane < 4) *reinterpret_cast<float4*>(&st[lane * 36 + 32]) = make_float4(M, L, 0.f, 0.f);
                __syncwarp();
                const int bh = item / TPB, tile = item % TPB;
#pragma unroll
                for (int k = 0; k < 2; k++) {
                    const int u = lane + 32 * k;
                    if (u < 4 * PUNITS) {
                        const int s4 = u / PUNITS, uu = u % PUNITS;
                        st_ll128(&g_part[((bh * 4 + s4) * TPB + tile) * PUNITS + uu], __float_as_uint(st[u * 3]),
                                 __float_as_uint(st[u * 3 + 1]), __float_as_uint(st[u * 3 + 2]), tag);
                    }
                }
            }
            if (++pi == NPRE) { pi = 0; ph ^= 1; }
        }
        if (tid == 0) PROF(4);
        if (!role) return;

        {
            const uint32_t* wrow = reinterpret_cast<const uint32_t*>(sm.ring + (2 * pi) * TILE_BYTES) + tid;
            uint32_t w[32];
#pragma unroll
            for (int r = 0; r < 32; r++) w[r] = wrow[r * 256];
            mbar_wait(smem_u32(&sm.o_ready), 0);
            if (tid == 0) PROF(5);
            float y00 = 0.f, y01 = 0.f, y10 = 0.f, y11 = 0.f, z00 = 0.f, z01 = 0.f, z10 = 0.f, z11 = 0.f;
#pragma unroll
            for (int r = 0; r < 32; r += 2) {
                const float4 o = *reinterpret_cast<const float4*>(&sm.so[r]);
                const float l0 = bf_lo(w[r]), h0 = bf_hi(w[r]), l1 = bf_lo(w[r + 1]), h1 = bf_hi(w[r + 1]);
                y00 = fmaf(o.x, l0, y00);
                y01 = fmaf(o.x, h0, y01);
                y10 = fmaf(o.y, l0, y10);
                y11 = fmaf(o.y, h0, y11);
                z00 = fmaf(o.z, l1, z00);
                z01 = fmaf(o.z, h1, z01);
                z10 = fmaf(o.w, l1, z10);
                z11 = fmaf(o.w, h1, z11);
            }
            st_ll64x2(&g_y[((tid >> 2) * NROLE + cta) * 4 + (tid & 3)], __float_as_uint(y00 + z00), __float_as_uint(y01 + z01), tag);
            st_ll64x2(&g_y[((64 + (tid >> 2)) * NROLE + cta) * 4 + (tid & 3)], __float_as_uint(y10 + z10), __float_as_uint(y11 + z11), tag);
        }
        if (tid == 0) PROF(6);
        {
            const uint4* src = &g_y[cta * NROLE * 4 + tid * 2];
            uint4 a, b;
            unsigned n = 0;
            do {
                a = ld_ll64x2(src);
                b = ld_ll64x2(src + 1);
                if (++n > SPIN_LIMIT) __trap();
            } while (a.y != tag || a.w != tag || b.y != tag || b.w != tag);
            float v[4] = {__uint_as_float(a.x), __uint_as_float(a.z), __uint_as_float(b.x), __uint_as_float(b.z)};
            xreduce<2>(v, 2, lane & 2);
            xreduce<1>(v, 4, lane & 4);
            v[0] += __shfl_xor_sync(0xffffffffu, v[0], 8);
            v[0] += __shfl_xor_sync(0xffffffffu, v[0], 16);
            if (lane < 8) sm.fred[warp][(lane & 1) * 4 + ((lane >> 1) & 1) * 2 + ((lane >> 2) & 1)] = v[0];
            bar_sync(BAR_CONS, NCONS);
            if (tid < 8) {
                float s = 0.f;
#pragma unroll
                for (int w = 0; w < 8; w++) s += sm.fred[w][tid];
                out[cta * 8 + tid] = __float2bfloat16_rn(xfin + rbf(rbf(s) * sm.sg[tid]));
            }
        }
        if (tid == 0) PROF(7);
    } else if (warp < 12) {
        __syncthreads();
        if (!role) return;
        const int a = tid - NCONS, aw = warp - 8;
        auto wait_progress = [&](int need) {
            unsigned n = 0;
            while (sm.progress < need) {
                __nanosleep(100);
                if (++n > SPIN_LIMIT) __trap();
            }
        };
        wait_progress(NPRE * G);
        const uint32_t tag = sm.tag;
        {
            float v0 = 0.f, v1 = 0.f;
#pragma unroll
            for (int k = 0; k < 3; k++) {
                const int u = a + 128 * k;
                if (u < NFFN * 4) {
                    uint4 r;
                    unsigned n = 0;
                    do {
                        r = ld_ll64x2(&g_f[cta * NFFN * 4 + u]);
                        if (++n > SPIN_LIMIT) __trap();
                    } while (r.y != tag || r.w != tag);
                    v0 += __uint_as_float(r.x);
                    v1 += __uint_as_float(r.z);
                }
            }
#pragma unroll
            for (int o = 4; o < 32; o <<= 1) {
                v0 += __shfl_xor_sync(0xffffffffu, v0, o);
                v1 += __shfl_xor_sync(0xffffffffu, v1, o);
            }
            if (lane < 4) *reinterpret_cast<float2*>(&sm.comb2[aw][lane * 2]) = make_float2(v0, v1);
            bar_sync(BAR_AUX, NAUX);
            if (a < 8) {
                const float fv = rbf(sm.comb2[0][a] + sm.comb2[1][a] + sm.comb2[2][a] + sm.comb2[3][a]);
                sm.sg[a] = rbf(__fdiv_rn(fv, 1.0f + expf(-fv)));
            }
            bar_sync(BAR_AUX, NAUX);
        }
#pragma unroll 1
        for (int b = 0; b < 2; b++) {
            const int bh = b * NH + (cta >> 2);
            wait_progress((bh + 1) * TPB + (NPRE + 1) * G);
            const uint4* src = &g_part[(bh * 4 + (cta & 3)) * TPB * PUNITS + a];
            unsigned pend = 0x3f, n = 0;
            while (pend) {
                uint4 r[6];
#pragma unroll
                for (int k = 0; k < 6; k++)
                    if (pend & (1u << k)) r[k] = ld_ll128(src + 128 * k);
#pragma unroll
                for (int k = 0; k < 6; k++)
                    if ((pend & (1u << k)) && r[k].w == tag) {
                        float* dst = &sm.comb[(a + 128 * k) * 3];
                        dst[0] = __uint_as_float(r[k].x);
                        dst[1] = __uint_as_float(r[k].y);
                        dst[2] = __uint_as_float(r[k].z);
                        pend &= ~(1u << k);
                    }
                if (++n > SPIN_LIMIT) __trap();
            }
            bar_sync(BAR_AUX, NAUX);
            const float M = warp_max(fmaxf(sm.comb[lane * 36 + 32], sm.comb[(lane + 32) * 36 + 32]));
            const int t0 = aw * 16;
            const float2 ml = *reinterpret_cast<const float2*>(&sm.comb[(t0 + (lane & 15)) * 36 + 32]);
            const float wt = ex2(ml.x - M);
            float o = 0.f;
#pragma unroll
            for (int i = 0; i < 16; i++) o = fmaf(__shfl_sync(0xffffffffu, wt, i), sm.comb[(t0 + i) * 36 + lane], o);
            float L = wt * ml.y;
#pragma unroll
            for (int of = 8; of; of >>= 1) L += __shfl_xor_sync(0xffffffffu, L, of);
            sm.comb2[aw][lane] = o;
            if (lane == 0) sm.comb2[aw][32] = L;
            bar_sync(BAR_AUX, NAUX);
            if (aw == 0) {
                const float os = sm.comb2[0][lane] + sm.comb2[1][lane] + sm.comb2[2][lane] + sm.comb2[3][lane];
                const float Ls = sm.comb2[0][32] + sm.comb2[1][32] + sm.comb2[2][32] + sm.comb2[3][32];
                reinterpret_cast<float*>(&sm.so[lane])[b] = rbf(__fdividef(os, Ls));
                __syncwarp();
                if (b == 1 && lane == 0) mbar_arrive(smem_u32(&sm.o_ready));
            }
            if (b == 0) bar_sync(BAR_AUX, NAUX);
        }
        if (a == 0) PROF(8);
    } else {
        unsigned long long v = 0;
        if (lane == 0) {
            v = atomicAdd(&g_start, 1ull);
#pragma unroll
            for (int s = 0; s < NSLOTS; s++) {
                mbar_init(full0 + s * 8, (s & 1) ? 1 : 2);
                mbar_init(empty0 + s * 8, 8);
            }
            mbar_init(smem_u32(&sm.o_ready), 1);
            sm.progress = 0;
            asm volatile("fence.mbarrier_init.release.cluster;" ::: "memory");
            asm volatile("fence.proxy.async.shared::cta;" ::: "memory");
        }
        __syncthreads();
        uint64_t pol;
        asm volatile("createpolicy.fractional.L2::evict_first.b64 %0, 1.0;" : "=l"(pol));
        const unsigned char* kb = reinterpret_cast<const unsigned char*>(kc);
        const unsigned char* vb = reinterpret_cast<const unsigned char*>(vc);
        uint32_t tag = 0;
        int next = 0;
        unsigned int* ticket = nullptr;
        if (lane == 0) {
#pragma unroll
            for (int j = 0; j < NPRE; j++) {
                const size_t off = (size_t)(cta + j * G) * TILE_BYTES;
                sm.info[j] = cta + j * G;
                mbar_expect_tx(full0 + (2 * j) * 8, TILE_BYTES);
                bulk_load(ring + (2 * j) * TILE_BYTES, kb + off, TILE_BYTES, full0 + (2 * j) * 8, pol);
                mbar_expect_tx(full0 + (2 * j + 1) * 8, TILE_BYTES);
                bulk_load(ring + (2 * j + 1) * TILE_BYTES, vb + off, TILE_BYTES, full0 + (2 * j + 1) * 8, pol);
            }
            const unsigned long long epoch = v / (unsigned)G;
            tag = (uint32_t)epoch + 1u;
            if (tag == 0) tag = 0x80000000u;
            sm.tag = tag;
            ticket = &g_ticket[epoch & 1];
            if (cta == 0) g_ticket[(epoch + 1) & 1] = 0;
            next = (int)atomicAdd(ticket, 1u) + NPRE * G;
        }
        __syncwarp();
        bar_arrive(BAR_TAG, NCONS + 32);
        tag = __shfl_sync(0xffffffffu, tag, 0);
        auto fetch_q = [&](int item, int pj, uint4 r) {
            const uint4* src = &g_q[(item / TPB) * 32 + lane];
            unsigned n = 0;
            while (r.y != tag || r.w != tag) {
                r = ld_ll64x2(src);
                if (++n > SPIN_LIMIT) __trap();
            }
            *reinterpret_cast<uint2*>(&sm.qs[pj][lane * 2]) = make_uint2(r.x, r.z);
            __syncwarp();
            if (lane == 0) mbar_arrive(full0 + (2 * pj) * 8);
        };
        for (int j = 0; j < NPRE; j++) {
            if (j == 0) __nanosleep(1500);
            fetch_q(cta + j * G, j, make_uint4(0, ~tag, 0, ~tag));
        }
        int pi = 0;
        uint32_t ph = 0;
        for (;;) {
            const int item = __shfl_sync(0xffffffffu, next, 0);
            mbar_wait(empty0 + (2 * pi) * 8, ph);
            const uint32_t fk = full0 + (2 * pi) * 8, fv = fk + 8;
            if (item >= NITEMS) {
                if (lane == 0) {
                    sm.info[pi] = -1;
                    if (role) {
                        mbar_expect_tx(fk, TILE_BYTES);
                        bulk_load(ring + (2 * pi) * TILE_BYTES, wo + (size_t)cta * 32 * DM, TILE_BYTES, fk, pol);
                    } else {
                        mbar_arrive(fk);
                    }
                    mbar_arrive(fk);
                    sm.progress = 2 * NITEMS;
                    PROF(9);
                }
                break;
            }
            const size_t off = (size_t)item * TILE_BYTES;
            if (lane == 0) {
                sm.info[pi] = item;
                mbar_expect_tx(fk, TILE_BYTES);
                bulk_load(ring + (2 * pi) * TILE_BYTES, kb + off, TILE_BYTES, fk, pol);
                next = (int)atomicAdd(ticket, 1u) + NPRE * G;
                sm.progress = item;
            }
            const uint4 r = ld_ll64x2(&g_q[(item / TPB) * 32 + lane]);
            mbar_wait(empty0 + (2 * pi + 1) * 8, ph);
            if (lane == 0) {
                mbar_expect_tx(fv, TILE_BYTES);
                bulk_load(ring + (2 * pi + 1) * TILE_BYTES, vb + off, TILE_BYTES, fv, pol);
            }
            fetch_q(item, pi, r);
            if (++pi == NPRE) { pi = 0; ph ^= 1; }
        }
    }
}

}

extern "C" void kernel_launch(void* const* d_in, const int* in_sizes, int n_in, void* d_out, int out_size) {
    (void)in_sizes; (void)n_in; (void)out_size;
    static int grid = 0;
    if (grid == 0) {
        int dev = 0, sms = 0;
        cudaGetDevice(&dev);
        cudaDeviceGetAttribute(&sms, cudaDevAttrMultiProcessorCount, dev);
        cudaFuncSetAttribute(fused_decode_kernel, cudaFuncAttributeMaxDynamicSharedMemorySize, (int)sizeof(Smem));
        grid = sms < NROLE ? NROLE : (sms > 160 ? 160 : sms);
    }
    fused_decode_kernel<<<grid, NTHREADS, sizeof(Smem)>>>(
        (const __nv_bfloat16*)d_in[0], (const __nv_bfloat16*)d_in[1], (const __nv_bfloat16*)d_in[2],
        (const __nv_bfloat16*)d_in[3], (const __nv_bfloat16*)d_in[4], (const __nv_bfloat16*)d_in[6],
        (const __nv_bfloat16*)d_in[7], (const __nv_bfloat16*)d_in[8], (__nv_bfloat16*)d_out);
}
```

```cpp
#include <cuda_runtime.h>
#include <cuda.h>
#include <cuda_bf16.h>
#include <stdint.h>

namespace {

constexpr int DM = 512, NH = 32, SK = 8192, DH = 128, FF = 1376;
constexpr int NBH = 2 * NH;
constexpr int TILE_KEYS = 64;
constexpr int TILE_BYTES = TILE_KEYS * DH * 2;
constexpr int TPB = SK / TILE_KEYS;
constexpr int NITEMS = NBH * TPB;
constexpr int NSLOT = 6;
constexpr int WIN = 3;
constexpr int WIN0 = 4;
constexpr int NSTATIC = 3;
constexpr int GATE = 64;
constexpr int FSW = 64;
static_assert(NSTATIC + 2 <= NSLOT - 1 && WIN0 <= 2 * NSTATIC, "first ring pass: static items, FFN weights, wq");
constexpr int NG = 2 * NSLOT;
constexpr int NCONS = 256, NAUX = 128, NTHREADS = NCONS + NAUX + 64;
constexpr int NROLE = 128;
constexpr int NFFN = FF / 16;
constexpr int FFN_ITEM = -3;
constexpr float LOG2E = 1.4426950408889634f;
constexpr unsigned SPIN_LIMIT = 1u << 22;

__device__ unsigned long long g_ticket;
__device__ unsigned int g_cnt[NBH * 32];
__device__ uint4 g_q[NBH * 32];
__device__ uint4 g_part[NBH * 32 * TPB * 2];
__device__ uint4 g_f[NROLE * NFFN * 4];
__device__ uint4 g_y[NROLE * NROLE * 2];

struct __align__(128) Smem {
    unsigned char ring[NG * TILE_BYTES];
    uint32_t qs[NSLOT][64];
    uint4 sc[2][2][8];
    alignas(16) float comb[2][8][4];
    float comb2[4][8];
    float2 xn[DM];
    float redp[8][64];
    float redf[4][64];
    float hs[2][16];
    alignas(16) float2 so[32];
    alignas(16) uint32_t so_last[4];
    alignas(16) float fred[8][8];
    float sg[8];
    unsigned long long full[NG], empty[NG], ffn_done[2], qfull[NSLOT], tfull[NSLOT], o_pre, tag_ready,
        wo_full, q_ready, xn_ready, wq_done, wq_full;
    uint32_t qout[32];
    int info[NSLOT];
    volatile int progress;
    volatile uint32_t tag;
    unsigned ticket0, epoch;
    unsigned posted[2];
};

__device__ __forceinline__ uint32_t smem_u32(const void* p) { return (uint32_t)__cvta_generic_to_shared(p); }
__device__ __forceinline__ void mbar_init(uint32_t bar, uint32_t cnt) {
    asm volatile("mbarrier.init.shared::cta.b64 [%0], %1;" ::"r"(bar), "r"(cnt) : "memory");
}
__device__ __forceinline__ void mbar_expect_tx(uint32_t bar, uint32_t bytes) {
    asm volatile("mbarrier.arrive.expect_tx.shared::cta.b64 _, [%0], %1;" ::"r"(bar), "r"(bytes) : "memory");
}
__device__ __forceinline__ void mbar_arrive(uint32_t bar) {
    asm volatile("mbarrier.arrive.shared::cta.b64 _, [%0];" ::"r"(bar) : "memory");
}
__device__ __forceinline__ void mbar_wait(uint32_t bar, uint32_t parity) {
    uint32_t ok, n = 0;
    do {
        asm volatile("{\n.reg .pred p;\nmbarrier.try_wait.parity.shared::cta.b64 p, [%1], %2;\nselp.u32 %0, 1, 0, p;\n}"
                     : "=r"(ok) : "r"(bar), "r"(parity) : "memory");
        if (++n > SPIN_LIMIT) __trap();
    } while (!ok);
}
__device__ __forceinline__ bool mbar_test(uint32_t bar, uint32_t parity) {
    uint32_t ok;
    asm volatile("{\n.reg .pred p;\nmbarrier.test_wait.parity.shared::cta.b64 p, [%1], %2;\nselp.u32 %0, 1, 0, p;\n}"
                 : "=r"(ok) : "r"(bar), "r"(parity) : "memory");
    return ok;
}
__device__ __forceinline__ void bulk_load(uint32_t dst, const void* src, uint32_t bytes, uint32_t bar, uint64_t pol) {
    asm volatile("cp.async.bulk.shared::cluster.global.mbarrier::complete_tx::bytes.L2::cache_hint [%0], [%1], %2, [%3], %4;"
                 ::"r"(dst), "l"(src), "r"(bytes), "r"(bar), "l"(pol) : "memory");
}
__device__ __forceinline__ void tensor_load_2d(uint32_t dst, const CUtensorMap* tm, int c0, int c1, uint32_t bar) {
    asm volatile("cp.async.bulk.tensor.2d.shared::cluster.global.mbarrier::complete_tx::bytes [%0], [%1, {%3, %4}], [%2];"
                 ::"r"(dst), "l"(tm), "r"(bar), "r"(c0), "r"(c1) : "memory");
}
__device__ __forceinline__ void bar_sync(int id, int n) { asm volatile("bar.sync %0, %1;" ::"r"(id), "r"(n) : "memory"); }
__device__ __forceinline__ void st_ll64x2(uint4* p, uint32_t a, uint32_t b, uint32_t tag) {
    asm volatile("{\n.reg .b64 x, y;\nmov.b64 x, {%1, %3};\nmov.b64 y, {%2, %3};\nst.relaxed.gpu.global.v2.b64 [%0], {x, y};\n}"
                 ::"l"(p), "r"(a), "r"(b), "r"(tag) : "memory");
}
__device__ __forceinline__ void st_ll64(void* p, uint32_t a, uint32_t tag) {
    asm volatile("{\n.reg .b64 x;\nmov.b64 x, {%1, %2};\nst.relaxed.gpu.global.b64 [%0], x;\n}" ::"l"(p), "r"(a), "r"(tag) : "memory");
}
__device__ __forceinline__ uint4 ld_ll64x2(const uint4* p) {
    uint4 v;
    asm volatile("{\n.reg .b64 x, y;\nld.relaxed.gpu.global.v2.b64 {x, y}, [%4];\nmov.b64 {%0, %1}, x;\nmov.b64 {%2, %3}, y;\n}"
                 : "=r"(v.x), "=r"(v.y), "=r"(v.z), "=r"(v.w) : "l"(p) : "memory");
    return v;
}
__device__ __forceinline__ void st_t2x2(uint2* p, float a, float b, uint32_t t2) {
    asm volatile("st.relaxed.gpu.global.v2.b32 [%0], {%1, %2};" ::"l"(p), "r"((__float_as_uint(a) & ~3u) | t2),
                 "r"((__float_as_uint(b) & ~3u) | t2) : "memory");
}
__device__ __forceinline__ uint4 ld_t2x4(const uint4* p) {
    uint4 v;
    asm volatile("ld.relaxed.gpu.global.v4.b32 {%0,%1,%2,%3}, [%4];" : "=r"(v.x), "=r"(v.y), "=r"(v.z), "=r"(v.w) : "l"(p) : "memory");
    return v;
}
__device__ __forceinline__ bool ok_t2x4(const uint4& v, uint32_t t2) {
    return (((v.x ^ t2) | (v.y ^ t2) | (v.z ^ t2) | (v.w ^ t2)) & 3u) == 0u;
}
__device__ __forceinline__ void st_ll128(uint4* p, uint32_t a, uint32_t b, uint32_t c, uint32_t tag) {
    asm volatile("{\n.reg .b64 x, y;\n.reg .b128 z;\nmov.b64 x, {%1, %2};\nmov.b64 y, {%3, %4};\nmov.b128 z, {x, y};\n"
                 "st.relaxed.gpu.global.b128 [%0], z;\n}" ::"l"(p), "r"(a), "r"(b), "r"(c), "r"(tag) : "memory");
}
__device__ __forceinline__ uint4 ld_ll128(const uint4* p) {
    uint4 v;
    asm volatile("{\n.reg .b64 x, y;\n.reg .b128 z;\nld.relaxed.gpu.global.b128 z, [%4];\nmov.b128 {x, y}, z;\n"
                 "mov.b64 {%0, %1}, x;\nmov.b64 {%2, %3}, y;\n}"
                 : "=r"(v.x), "=r"(v.y), "=r"(v.z), "=r"(v.w) : "l"(p) : "memory");
    return v;
}
__device__ __forceinline__ void ldsm_x4(uint32_t addr, uint32_t& a0, uint32_t& a1, uint32_t& a2, uint32_t& a3) {
    asm volatile("ldmatrix.sync.aligned.m8n8.x4.shared.b16 {%0,%1,%2,%3}, [%4];"
                 : "=r"(a0), "=r"(a1), "=r"(a2), "=r"(a3) : "r"(addr) : "memory");
}
__device__ __forceinline__ void ldsm_x4_t(uint32_t addr, uint32_t& a0, uint32_t& a1, uint32_t& a2, uint32_t& a3) {
    asm volatile("ldmatrix.sync.aligned.m8n8.x4.trans.shared.b16 {%0,%1,%2,%3}, [%4];"
                 : "=r"(a0), "=r"(a1), "=r"(a2), "=r"(a3) : "r"(addr) : "memory");
}
__device__ __forceinline__ void mma_bf16(float* d, uint32_t a0, uint32_t a1, uint32_t a2, uint32_t a3, uint32_t b0, uint32_t b1) {
    asm volatile("mma.sync.aligned.m16n8k16.row.col.f32.bf16.bf16.f32 {%0,%1,%2,%3}, {%4,%5,%6,%7}, {%8,%9}, {%0,%1,%2,%3};"
                 : "+f"(d[0]), "+f"(d[1]), "+f"(d[2]), "+f"(d[3]) : "r"(a0), "r"(a1), "r"(a2), "r"(a3), "r"(b0), "r"(b1));
}
__device__ __forceinline__ float bf_lo(uint32_t w) { return __uint_as_float(w << 16); }
__device__ __forceinline__ float bf_hi(uint32_t w) { return __uint_as_float(w & 0xffff0000u); }
__device__ __forceinline__ float rbf(float x) { return __bfloat162float(__float2bfloat16_rn(x)); }
__device__ __forceinline__ uint32_t bf_bits(float x) { return (uint32_t)__bfloat16_as_ushort(__float2bfloat16_rn(x)); }
__device__ __forceinline__ float ex2(float x) { float y; asm("ex2.approx.ftz.f32 %0, %1;" : "=f"(y) : "f"(x)); return y; }
__device__ __forceinline__ int f2ord(float f) { int i = __float_as_int(f); return i ^ ((i >> 31) & 0x7fffffff); }
__device__ __forceinline__ float ord2f(int i) { return __int_as_float(i ^ ((i >> 31) & 0x7fffffff)); }
__device__ __forceinline__ float warp_max(float v) { return ord2f(__reduce_max_sync(0xffffffffu, f2ord(v))); }

template <int N>
__device__ __forceinline__ void xreduce(float* v, int mask, bool upper) {
#pragma unroll
    for (int i = 0; i < N; i++) {
        float keep = upper ? v[N + i] : v[i];
        float send = upper ? v[i] : v[N + i];
        v[i] = keep + __shfl_xor_sync(0xffffffffu, send, mask);
    }
}
__device__ __forceinline__ void fma8(float* acc0, float* acc1, const uint4& w, float2 x) {
    const uint32_t ww[4] = {w.x, w.y, w.z, w.w};
#pragma unroll
    for (int j = 0; j < 4; j++) {
        float lo = bf_lo(ww[j]), hi = bf_hi(ww[j]);
        acc0[2 * j] = fmaf(x.x, lo, acc0[2 * j]);
        acc0[2 * j + 1] = fmaf(x.x, hi, acc0[2 * j + 1]);
        acc1[2 * j] = fmaf(x.y, lo, acc1[2 * j]);
        acc1[2 * j + 1] = fmaf(x.y, hi, acc1[2 * j + 1]);
    }
}

enum { BAR_CONS = 1, BAR_AUX = 2, BAR_GRP = 3 };
constexpr float NEG_BF16_MAX = -3.3895313892515355e38f;

__global__ void __launch_bounds__(NTHREADS, 1)
fused_decode_kernel(const __grid_constant__ CUtensorMap tm_wq, const __grid_constant__ CUtensorMap tm_wg,
                    const __grid_constant__ CUtensorMap tm_wu, const __nv_bfloat16* __restrict__ x, const __nv_bfloat16* __restrict__ kc,
                    const __nv_bfloat16* __restrict__ vc,
                    const __nv_bfloat16* __restrict__ wo, const __nv_bfloat16* __restrict__ wd,
                    __nv_bfloat16* __restrict__ out) {
    extern __shared__ __align__(1024) unsigned char smem_raw[];
    Smem& sm = *reinterpret_cast<Smem*>(smem_raw);
    const int tid = threadIdx.x, lane = tid & 31, warp = tid >> 5;
    const int cta = blockIdx.x, G = gridDim.x;
    const bool role = cta < NROLE;
    const int fc = cta - (G - NFFN);
    const uint32_t ring = smem_u32(sm.ring);
    const uint32_t full0 = smem_u32(&sm.full[0]), empty0 = smem_u32(&sm.empty[0]);

    const int bw = (warp >> 2) & 1;
    uint4 xa = make_uint4(0, 0, 0, 0), xb = xa;
    uint2 xo = make_uint2(0, 0);
    __nv_bfloat16 xfin_raw = __float2bfloat16(0.f);
    if (warp < 8) {
        xa = *reinterpret_cast<const uint4*>(x + bw * DM + lane * 16);
        xb = *reinterpret_cast<const uint4*>(x + bw * DM + lane * 16 + 8);
        xo = *reinterpret_cast<const uint2*>(x + tid * 4);
        if (role && tid < 8) xfin_raw = x[(cta ^ FSW) * 8 + tid];
    }
    const unsigned char* kb = reinterpret_cast<const unsigned char*>(kc);
    const unsigned char* vb = reinterpret_cast<const unsigned char*>(vc);
    uint64_t pol = 0;
    unsigned long long v = 0;
    if (lane == 0) {
        constexpr int NBAR = 2 * NG + 2 + 2 * NSLOT + 6;
        if (warp == 12) {
            asm volatile("createpolicy.fractional.L2::evict_first.b64 %0, 1.0;" : "=l"(pol));
#pragma unroll
            for (int s = 0; s < WIN0; s++) {
                const int item = cta + (s >> 1) * G;
                mbar_init(full0 + s * 8, 1);
                asm volatile("fence.mbarrier_init.release.cluster;" ::: "memory");
                sm.info[s >> 1] = item;
                mbar_expect_tx(full0 + s * 8, TILE_BYTES);
                bulk_load(ring + s * TILE_BYTES, ((s & 1) ? vb : kb) + (size_t)item * TILE_BYTES, TILE_BYTES, full0 + s * 8, pol);
                if (s == 0) {
                    mbar_init(smem_u32(&sm.wq_full), 1);
                    asm volatile("fence.mbarrier_init.release.cluster;" ::: "memory");
                    if (role) {
                        mbar_expect_tx(smem_u32(&sm.wq_full), 2 * TILE_BYTES);
                        tensor_load_2d(ring + (NG - 2) * TILE_BYTES, &tm_wq, cta * 32, 0, smem_u32(&sm.wq_full));
                        tensor_load_2d(ring + (NG - 1) * TILE_BYTES, &tm_wq, cta * 32, 256, smem_u32(&sm.wq_full));
                    }
                }
            }
        } else if (warp == 13) {
            asm volatile("prefetch.tensormap [%0];" ::"l"(&tm_wq) : "memory");
            v = atomicAdd(&g_ticket, 1ull);
            asm volatile("prefetch.tensormap [%0];" ::"l"(&tm_wg) : "memory");
            asm volatile("prefetch.tensormap [%0];" ::"l"(&tm_wu) : "memory");
            sm.progress = 0;
            sm.posted[0] = sm.posted[1] = 0;
            sm.so_last[0] = sm.so_last[1] = sm.so_last[2] = sm.so_last[3] = ~0u;
        } else {
            for (int i = WIN0 + warp; i < NBAR; i += 12)
                mbar_init(full0 + i * 8, i < NG ? 1 : i < 2 * NG + 2 ? 4 : i < NBAR - 2 ? 1 : 8);
            asm volatile("fence.mbarrier_init.release.cluster;" ::: "memory");
        }
    }
    __syncthreads();

    if (warp < 8) {
        uint2* const ydst = reinterpret_cast<uint2*>(g_y) + ((tid >> 2) * NROLE + cta) * 4 + (tid & 3);
        const float xfin = __bfloat162float(xfin_raw);

        {
            const uint32_t xw[8] = {xa.x, xa.y, xa.z, xa.w, xb.x, xb.y, xb.z, xb.w};
            float s = 0.f;
#pragma unroll
            for (int j = 0; j < 8; j++) s += bf_lo(xw[j]) + bf_hi(xw[j]);
#pragma unroll
            for (int o = 16; o; o >>= 1) s += __shfl_xor_sync(0xffffffffu, s, o);
            const float mean = s * (1.0f / DM);
            float v = 0.f;
#pragma unroll
            for (int j = 0; j < 8; j++) {
                float a = bf_lo(xw[j]) - mean, b = bf_hi(xw[j]) - mean;
                v = fmaf(a, a, v);
                v = fmaf(b, b, v);
            }
#pragma unroll
            for (int o = 16; o; o >>= 1) v += __shfl_xor_sync(0xffffffffu, v, o);
            const float mb = rbf(mean);
            const float den = rbf(__fsqrt_rn(rbf(rbf(v * (1.0f / DM)) + 1e-5f)));
            float* xnf = reinterpret_cast<float*>(sm.xn);
            const int e = (tid & 127) * 4;
            xnf[(e + 0) * 2 + bw] = rbf(__fdiv_rn(rbf(bf_lo(xo.x) - mb), den));
            xnf[(e + 1) * 2 + bw] = rbf(__fdiv_rn(rbf(bf_hi(xo.x) - mb), den));
            xnf[(e + 2) * 2 + bw] = rbf(__fdiv_rn(rbf(bf_lo(xo.y) - mb), den));
            xnf[(e + 3) * 2 + bw] = rbf(__fdiv_rn(rbf(bf_hi(xo.y) - mb), den));
        }
        __syncwarp();
        if (lane == 0) mbar_arrive(smem_u32(&sm.xn_ready));
        mbar_wait(smem_u32(&sm.xn_ready), 0);

        if (role) {
            const uint4* wqs = reinterpret_cast<const uint4*>(sm.ring + (NG - 2) * TILE_BYTES);
            mbar_wait(smem_u32(&sm.wq_full), 0);
            float acc[16];
#pragma unroll
            for (int j = 0; j < 16; j++) acc[j] = 0.f;
#pragma unroll
            for (int i = 0; i < 8; i++) fma8(acc, acc + 8, wqs[i * 256 + tid], sm.xn[(tid >> 2) + 64 * i]);
            xreduce<8>(acc, 16, lane & 16);
            xreduce<4>(acc, 8, lane & 8);
            xreduce<2>(acc, 4, lane & 4);
            const int pos = ((lane >> 4) & 1) * 32 + (lane & 3) * 8 + ((lane >> 3) & 1) * 4 + ((lane >> 2) & 1) * 2;
            *reinterpret_cast<float2*>(&sm.redp[warp][pos]) = make_float2(acc[0], acc[1]);
        }
        if (lane == 0) mbar_arrive(smem_u32(&sm.wq_done));
        bar_sync(BAR_CONS, NCONS);
        mbar_wait(smem_u32(&sm.tag_ready), 0);
        const uint32_t tag = sm.tag, tag2 = sm.epoch % 3u + 1u;
        if (role && warp == 0) {
            float a = 0.f, b = 0.f;
#pragma unroll
            for (int w = 0; w < 8; w++) {
                float2 t = *reinterpret_cast<const float2*>(&sm.redp[w][lane * 2]);
                a += t.x;
                b += t.y;
            }
            const int bh = (lane >> 4) * NH + (cta >> 2);
            unsigned long long* qdst = reinterpret_cast<unsigned long long*>(g_q) + bh * 64 + (cta & 3) * 16 + (lane & 15);
            const uint32_t qw = bf_bits(a) | (bf_bits(b) << 16);
            if (bh < 8) st_ll64(qdst, qw, tag);
            sm.qout[lane] = qw;
            __syncwarp();
            if (lane == 0) mbar_arrive(smem_u32(&sm.q_ready));
        }

        const int grp = warp >> 2, wg = warp & 3;
        const int g = lane >> 2, q4 = lane & 3;
        const bool diag = (q4 == (g >> 1));
        const int lr = lane & 7, lm = lane >> 3;
        const uint32_t k_row = (uint32_t)((wg * 16 + (lm & 1) * 8 + lr) * 256 + (lm >> 1) * 128);
        const uint32_t v_row0 = (uint32_t)(((lm >> 1) * 8 + lr) * 256 + wg * 64 + (((lr + (lm & 1)) & 3) << 4));
        const uint32_t v_row1 = (uint32_t)(((lm >> 1) * 8 + lr) * 256 + wg * 64 + (((lr + (lm & 1) + 2) & 3) << 4));
        int pi = grp, item = -1;
        uint32_t ph = 0;
#pragma unroll 1
        for (int pass = role ? 0 : 1; pass < 2; ++pass) {
        if (pass)
        for (int it = 0;;) {
            const uint32_t kslot = ring + (2 * pi) * TILE_BYTES, vslot = kslot + TILE_BYTES;
            const uint32_t gk = (2 * pi) * 8, gv = gk + 8;
            mbar_wait(full0 + gk, ph);
            item = *reinterpret_cast<volatile int*>(&sm.info[pi]);
            if (item == FFN_ITEM) {
                mbar_wait(smem_u32(&sm.qfull[pi]), ph);
                if (lane == 0) {
                    mbar_arrive(empty0 + gk);
                    mbar_arrive(empty0 + gv);
                }
                pi += 2;
                if (pi >= NSLOT) { pi -= NSLOT; ph ^= 1; }
                continue;
            }
            if (item < 0) break;
            mbar_wait(smem_u32(&sm.qfull[pi]), ph);
            float sa[4] = {0.f, 0.f, 0.f, 0.f}, sb[4] = {0.f, 0.f, 0.f, 0.f};
#pragma unroll
            for (int s = 0; s < 8; s++) {
                uint32_t a0, a1, a2, a3;
                ldsm_x4(kslot + k_row + (((s + lr) & 7) << 4), a0, a1, a2, a3);
                const int j = ((s + g) & 7) * 4 + q4;
                mma_bf16((s & 1) ? sb : sa, a0, a1, a2, a3, sm.qs[pi][j], sm.qs[pi][32 + j]);
            }
            float s0 = (g & 1) ? sa[1] + sb[1] : sa[0] + sb[0];
            float s1 = (g & 1) ? sa[3] + sb[3] : sa[2] + sb[2];
            s0 = rbf(rbf(s0) * 0.08838834764831845f);
            s1 = rbf(rbf(s1) * 0.08838834764831845f);
            uint4* scb = sm.sc[grp][it & 1];
            if (diag) reinterpret_cast<uint32_t*>(&scb[g])[wg] = (__float_as_uint(s0) >> 16) | (__float_as_uint(s1) & 0xffff0000u);
            __syncwarp();
            if (lane == 0) mbar_arrive(empty0 + gk);
            bar_sync(BAR_GRP + grp, 128);
            const uint4 sv = scb[g];
            const uint32_t sw[4] = {sv.x, sv.y, sv.z, sv.w};
            float mx = NEG_BF16_MAX;
#pragma unroll
            for (int j = 0; j < 4; j++) mx = fmaxf(mx, fmaxf(bf_lo(sw[j]), bf_hi(sw[j])));
            const float M = warp_max(mx);
            uint32_t b0[4], b1[4];
            float L = 0.f;
#pragma unroll
            for (int j = 0; j < 4; j++) {
                const uint32_t p0 = bf_bits(ex2((bf_lo(sw[j]) - M) * LOG2E)), p1 = bf_bits(ex2((bf_hi(sw[j]) - M) * LOG2E));
                L += __uint_as_float(p0 << 16) + __uint_as_float(p1 << 16);
                b0[j] = diag ? ((g & 1) ? (p0 << 16) : p0) : 0u;
                b1[j] = diag ? ((g & 1) ? (p1 << 16) : p1) : 0u;
            }
            L += __shfl_xor_sync(0xffffffffu, L, 4);
            L += __shfl_xor_sync(0xffffffffu, L, 8);
            L += __shfl_xor_sync(0xffffffffu, L, 16);
            const uint32_t mt = (__float_as_uint(M) & 0xffff0000u) | tag;
            uint4* dst = &g_part[(((item / TPB) * 32 + wg * 8 + (q4 & 1) * 4 + (q4 >> 1) * 2 + (g >> 2)) * TPB + (item % TPB)) * 2 + ((g >> 1) & 1)];
            mbar_wait(full0 + gv, ph);
            float d0[4] = {0.f, 0.f, 0.f, 0.f}, d1[4] = {0.f, 0.f, 0.f, 0.f};
#pragma unroll
            for (int j = 0; j < 4; j++) {
                uint32_t a0, a1, a2, a3;
                ldsm_x4_t(vslot + j * 4096 + v_row0, a0, a1, a2, a3);
                mma_bf16(d0, a0, a1, a2, a3, b0[j], b1[j]);
                ldsm_x4_t(vslot + j * 4096 + v_row1, a0, a1, a2, a3);
                mma_bf16(d1, a0, a1, a2, a3, b0[j], b1[j]);
            }
            float e0 = d0[0] + d1[3], e1 = d0[1] + d0[2];
            const float e2 = d1[0] + d0[3], e3 = d1[1] + d1[2];
            e0 += __shfl_xor_sync(0xffffffffu, e2, 1);
            e1 += __shfl_xor_sync(0xffffffffu, e3, 1);
            e0 = ((q4 & 2) ? e1 : e0) + __shfl_xor_sync(0xffffffffu, (q4 & 2) ? e0 : e1, 2);
            e1 = __shfl_xor_sync(0xffffffffu, e0, 4);
            if (!(g & 1)) st_ll128(dst, __float_as_uint(e0), __float_as_uint(e1), __float_as_uint(L), mt);
            __syncwarp();
            if (lane == 0) mbar_arrive(empty0 + gv);
            if (lane == 0 && atomicInc(&sm.posted[grp], 3u) == 3u) {
                asm volatile("red.relaxed.gpu.global.add.u32 [%0], 1;" ::"l"(&g_cnt[(item / TPB) * 32]) : "memory");
            }
            ++it;
            pi += 2;
            if (pi >= NSLOT) { pi -= NSLOT; ph ^= 1; }
        }
        if (!role) return;

        {
            int pw = pi + ((item == -1) ? 2 : 1);
            if (pw >= NSLOT) pw -= NSLOT;
            const uint32_t* wrow = reinterpret_cast<const uint32_t*>(sm.ring + (2 * pw) * TILE_BYTES) + tid;
            const uint32_t ytag = pass ? tag2 : 0u;
            const uint32_t wpar = pass ? 0u : 1u;
            mbar_wait(smem_u32(&sm.o_pre), wpar);
            float4 o[16];
#pragma unroll
            for (int r = 0; r < 16; r++) o[r] = *reinterpret_cast<const float4*>(&sm.so[2 * r]);
            mbar_wait(smem_u32(&sm.wo_full), wpar);
            float y00 = 0.f, y01 = 0.f, y10 = 0.f, y11 = 0.f, z00 = 0.f, z01 = 0.f, z10 = 0.f, z11 = 0.f;
            uint32_t wl[4];
#pragma unroll
            for (int r = 0; r < 16; r++) {
                const uint32_t w0 = wrow[(2 * r) * 256], w1 = wrow[(2 * r + 1) * 256];
                const float l0 = bf_lo(w0), h0 = bf_hi(w0), l1 = bf_lo(w1), h1 = bf_hi(w1);
                y00 = fmaf(o[r].x, l0, y00);
                y01 = fmaf(o[r].x, h0, y01);
                z00 = fmaf(o[r].z, l1, z00);
                z01 = fmaf(o[r].z, h1, z01);
                if (r < 14) {
                    y10 = fmaf(o[r].y, l0, y10);
                    y11 = fmaf(o[r].y, h0, y11);
                    z10 = fmaf(o[r].w, l1, z10);
                    z11 = fmaf(o[r].w, h1, z11);
                } else {
                    wl[2 * (r - 14)] = w0;
                    wl[2 * (r - 14) + 1] = w1;
                }
            }
            st_t2x2(ydst, y00 + z00, y01 + z01, ytag);
            uint4 ol;
            unsigned n = 0;
            do {
                asm volatile("ld.volatile.shared.v4.b32 {%0,%1,%2,%3}, [%4];" : "=r"(ol.x), "=r"(ol.y), "=r"(ol.z), "=r"(ol.w)
                             : "r"(smem_u32(sm.so_last)) : "memory");
                if (++n > (SPIN_LIMIT << 4)) __trap();
            } while (pass && (ol.x == ~0u || ol.y == ~0u || ol.z == ~0u || ol.w == ~0u));
            y10 = fmaf(__uint_as_float(ol.x), bf_lo(wl[0]), y10);
            y11 = fmaf(__uint_as_float(ol.x), bf_hi(wl[0]), y11);
            z10 = fmaf(__uint_as_float(ol.y), bf_lo(wl[1]), z10);
            z11 = fmaf(__uint_as_float(ol.y), bf_hi(wl[1]), z11);
            y10 = fmaf(__uint_as_float(ol.z), bf_lo(wl[2]), y10);
            y11 = fmaf(__uint_as_float(ol.z), bf_hi(wl[2]), y11);
            z10 = fmaf(__uint_as_float(ol.w), bf_lo(wl[3]), z10);
            z11 = fmaf(__uint_as_float(ol.w), bf_hi(wl[3]), z11);
            st_t2x2(ydst + 64 * NROLE * 4, y10 + z10, y11 + z11, ytag);
        }
        {
            const uint4* ysrc = &g_y[(cta ^ FSW) * NROLE * 2 + tid];
            uint4 ya = make_uint4(0u, 0u, 0u, 0u);
            if (pass) {
                bool ok = false;
                unsigned n = 0;
                for (;;) {
                    if (!ok) ya = ld_t2x4(ysrc);
                    ok = ok_t2x4(ya, tag2);
                    if (__all_sync(0xffffffffu, ok)) break;
                    if (++n > SPIN_LIMIT) __trap();
                }
            }
            float v[4] = {__uint_as_float(ya.x & ~3u), __uint_as_float(ya.y & ~3u), __uint_as_float(ya.z & ~3u), __uint_as_float(ya.w & ~3u)};
            xreduce<2>(v, 2, lane & 2);
            xreduce<1>(v, 4, lane & 4);
            v[0] += __shfl_xor_sync(0xffffffffu, v[0], 8);
            v[0] += __shfl_xor_sync(0xffffffffu, v[0], 16);
            if (lane < 8) sm.fred[(lane & 1) * 4 + ((lane >> 1) & 1) * 2 + (lane >> 2)][warp] = v[0];
            const float gate = sm.sg[tid & 7];
            bar_sync(BAR_CONS, NCONS);
            if (tid < 8) {
                const float4 f0 = *reinterpret_cast<const float4*>(&sm.fred[tid][0]), f1 = *reinterpret_cast<const float4*>(&sm.fred[tid][4]);
                const float s = ((f0.x + f0.y) + (f0.z + f0.w)) + ((f1.x + f1.y) + (f1.z + f1.w));
                const __nv_bfloat16 r = __float2bfloat16_rn(xfin + rbf(rbf(s) * gate));
                if (pass) out[(cta ^ FSW) * 8 + tid] = r;
            }
        }
        }
    } else if (warp < 12) {
        const int a = tid - NCONS, aw = warp - 8;
        auto wait_progress = [&](int need) {
            unsigned n = 0;
            while (sm.progress < need) {
                __nanosleep(100);
                if (++n > SPIN_LIMIT) __trap();
            }
        };
        if (role) {
            uint4* mb = &g_part[(((cta >> 5) + 60) * 32 + (cta & 31)) * TPB * 2 + a];
            st_ll128(mb, 0u, 0u, 0u, 0u);
            st_ll128(mb + 128, 0u, 0u, 0u, 0u);
            asm volatile("fence.acq_rel.gpu;" ::: "memory");
            bar_sync(BAR_AUX, NAUX);
            if (aw == 0) {
                mbar_wait(smem_u32(&sm.q_ready), 0);
                const int bh = (lane >> 4) * NH + (cta >> 2);
                if (bh >= 8)
                    st_ll64(reinterpret_cast<unsigned long long*>(g_q) + bh * 64 + (cta & 3) * 16 + (lane & 15), sm.qout[lane], sm.tag);
            }
        }
        if (fc >= 0) {
            const unsigned char* fw = sm.ring + (2 * NSTATIC) * TILE_BYTES;
            mbar_wait(smem_u32(&sm.xn_ready), 0);
            float acc[32];
#pragma unroll
            for (int j = 0; j < 32; j++) acc[j] = 0.f;
            mbar_wait(full0 + (2 * NSTATIC) * 8, 0);
            mbar_wait(full0 + (2 * NSTATIC + 1) * 8, 0);
#pragma unroll 2
            for (int i = 0; i < 8; i++) {
                const float2 xv = sm.xn[(a >> 1) + 64 * i];
                fma8(acc, acc + 8, reinterpret_cast<const uint4*>(fw)[i * 128 + a], xv);
                fma8(acc + 16, acc + 24, reinterpret_cast<const uint4*>(fw + TILE_BYTES)[i * 128 + a], xv);
            }
            xreduce<16>(acc, 16, lane & 16);
            xreduce<8>(acc, 8, lane & 8);
            xreduce<4>(acc, 4, lane & 4);
            xreduce<2>(acc, 2, lane & 2);
            const int pos = ((lane >> 4) & 1) * 32 + ((lane >> 3) & 1) * 16 + (lane & 1) * 8 + ((lane >> 2) & 1) * 4 + ((lane >> 1) & 1) * 2;
            *reinterpret_cast<float2*>(&sm.redf[aw][pos]) = make_float2(acc[0], acc[1]);
            __syncwarp();
            if (lane == 0) mbar_arrive(smem_u32(&sm.ffn_done[0]));
            bar_sync(BAR_AUX, NAUX);
            if (aw == 0) {
                float g = rbf(sm.redf[0][lane] + sm.redf[1][lane] + sm.redf[2][lane] + sm.redf[3][lane]);
                float u = rbf(sm.redf[0][32 + lane] + sm.redf[1][32 + lane] + sm.redf[2][32 + lane] + sm.redf[3][32 + lane]);
                const float inner = 0.7978845608028654f * (g + 0.044715f * g * g * g);
                const float ge = rbf(0.5f * g * (1.0f + tanhf(inner)));
                sm.hs[lane >> 4][lane & 15] = rbf(ge * u);
            }
            bar_sync(BAR_AUX, NAUX);
            float f0[4] = {0.f, 0.f, 0.f, 0.f}, f1[4] = {0.f, 0.f, 0.f, 0.f};
            mbar_wait(full0 + (2 * NSTATIC + 2) * 8, 0);
#pragma unroll
            for (int r = 0; r < 16; r++) {
                const uint2 rd = reinterpret_cast<const uint2*>(fw + 2 * TILE_BYTES)[r * 128 + a];
                const float w4[4] = {bf_lo(rd.x), bf_hi(rd.x), bf_lo(rd.y), bf_hi(rd.y)};
                const float h0 = sm.hs[0][r], h1 = sm.hs[1][r];
#pragma unroll
                for (int j = 0; j < 4; j++) {
                    f0[j] = fmaf(h0, w4[j], f0[j]);
                    f1[j] = fmaf(h1, w4[j], f1[j]);
                }
            }
            mbar_wait(smem_u32(&sm.tag_ready), 0);
            const uint32_t tg = sm.tag;
            uint4* d0 = &g_f[((a >> 1) * NFFN + fc) * 4 + (a & 1) * 2];
            uint4* d1 = d0 + 64 * NFFN * 4;
            st_ll64x2(d0, __float_as_uint(f0[0]), __float_as_uint(f0[1]), tg);
            st_ll64x2(d0 + 1, __float_as_uint(f0[2]), __float_as_uint(f0[3]), tg);
            st_ll64x2(d1, __float_as_uint(f1[0]), __float_as_uint(f1[1]), tg);
            st_ll64x2(d1 + 1, __float_as_uint(f1[2]), __float_as_uint(f1[3]), tg);
            __syncwarp();
            if (lane == 0) mbar_arrive(smem_u32(&sm.ffn_done[1]));
        }
        if (!role) return;
        mbar_wait(smem_u32(&sm.tag_ready), 0);
        const uint32_t tag = sm.tag;
        const unsigned cnt_target = (sm.epoch + 1u) * (unsigned)TPB;
        auto gather_gate = [&]()
        {
            float v0 = 0.f, v1 = 0.f;
#pragma unroll
            for (int k = 0; k < 3; k++) {
                const int u = a + 128 * k;
                if (u < NFFN * 4) {
                    uint4 r;
                    unsigned n = 0;
                    do {
                        r = ld_ll64x2(&g_f[(cta ^ FSW) * NFFN * 4 + u]);
                        if (++n > SPIN_LIMIT) __trap();
                    } while (r.y != tag || r.w != tag);
                    v0 += __uint_as_float(r.x);
                    v1 += __uint_as_float(r.z);
                }
            }
#pragma unroll
            for (int o = 4; o < 32; o <<= 1) {
                v0 += __shfl_xor_sync(0xffffffffu, v0, o);
                v1 += __shfl_xor_sync(0xffffffffu, v1, o);
            }
            if (lane < 4) *reinterpret_cast<float2*>(&sm.comb2[aw][lane * 2]) = make_float2(v0, v1);
            bar_sync(BAR_AUX, NAUX);
            if (a < 8) {
                const float fv = rbf(sm.comb2[0][a] + sm.comb2[1][a] + sm.comb2[2][a] + sm.comb2[3][a]);
                sm.sg[a] = rbf(__fdiv_rn(fv, 1.0f + expf(-fv)));
            }
            bar_sync(BAR_AUX, NAUX);
        };
#pragma unroll 1
        for (int k = 0; k < 16; k++) {
            const int bh = (cta >> 5) + 4 * k;
            if (k == 8) gather_gate();
            const uint4* src = &g_part[(bh * 32 + (cta & 31)) * TPB * 2 + a];
            uint4 r0, r1;
            unsigned n = 0;
            wait_progress((bh + 1) * TPB);
            if (lane == 0) {
                unsigned c;
                for (;;) {
                    asm volatile("ld.relaxed.gpu.global.u32 %0, [%1];" : "=r"(c) : "l"(&g_cnt[bh * 32]) : "memory");
                    if ((int)(c - cnt_target) >= (k == 15 ? -GATE : 0)) break;
                    if (++n > SPIN_LIMIT) __trap();
                }
            }
            __syncwarp();
            n = 0;
            r0 = ld_ll128(src);
            r1 = ld_ll128(src + 128);
            for (;;) {
                const bool ok0 = (r0.w & 0xffffu) == tag, ok1 = (r1.w & 0xffffu) == tag;
                if (__all_sync(0xffffffffu, ok0 && ok1)) break;
                if (!ok0) r0 = ld_ll128(src);
                if (!ok1) r1 = ld_ll128(src + 128);
                if (++n > SPIN_LIMIT) __trap();
            }
            const float m0 = __uint_as_float(r0.w & 0xffff0000u), m1 = __uint_as_float(r1.w & 0xffff0000u);
            const float mw = warp_max(fmaxf(m0, m1));
            const float c0 = ex2((m0 - mw) * LOG2E), c1 = ex2((m1 - mw) * LOG2E);
            float v[4] = {fmaf(c0, __uint_as_float(r0.x), c1 * __uint_as_float(r1.x)), fmaf(c0, __uint_as_float(r0.y), c1 * __uint_as_float(r1.y)),
                          fmaf(c0, __uint_as_float(r0.z), c1 * __uint_as_float(r1.z)), 0.f};
            xreduce<2>(v, 16, lane & 16);
            xreduce<1>(v, 8, lane & 8);
            v[0] += __shfl_xor_sync(0xffffffffu, v[0], 4);
            v[0] += __shfl_xor_sync(0xffffffffu, v[0], 2);
            if ((lane & 6) == 0) sm.comb[k & 1][(lane & 1) * 4 + (lane >> 3)][aw] = (lane == 24) ? mw : v[0];
            bar_sync(BAR_AUX, NAUX);
            if (a < 4) {
                const float4 mm = *reinterpret_cast<const float4*>(sm.comb[k & 1][3]);
                const float4 oo = *reinterpret_cast<const float4*>(sm.comb[k & 1][(a >> 1) * 4 + (a & 1)]);
                const float4 ll = *reinterpret_cast<const float4*>(sm.comb[k & 1][2]);
                const float M = fmaxf(fmaxf(mm.x, mm.y), fmaxf(mm.z, mm.w));
                const float e0 = ex2((mm.x - M) * LOG2E), e1 = ex2((mm.y - M) * LOG2E), e2 = ex2((mm.z - M) * LOG2E), e3 = ex2((mm.w - M) * LOG2E);
                const float os = fmaf(e0, oo.x, e1 * oo.y) + fmaf(e2, oo.z, e3 * oo.w);
                const float Ls = fmaf(e0, ll.x, e1 * ll.y) + fmaf(e2, ll.z, e3 * ll.w);
                float* dst = (k == 15) ? reinterpret_cast<float*>(&sm.so_last[a]) : reinterpret_cast<float*>(&sm.so[(k & 7) * 4 + a]) + (k >> 3);
                *reinterpret_cast<volatile float*>(dst) = rbf(__fdividef(os, Ls));
            }
            if (aw == 0 && k == 14) {
                __syncwarp();
                if (lane == 0) mbar_arrive(smem_u32(&sm.o_pre));
            }
        }
    } else if (warp == 12) {
        if (lane != 0) return;
        int inflight = WIN0, skip = WIN0, ls = 0, win = WIN;
        uint32_t lph = 0;
        bool early = true;
        auto throttle = [&]() {
            if (early) {
                unsigned n = 0;
                while (inflight >= WIN0) {
                    if (mbar_test(full0 + ls * 8, lph)) {
                        inflight--;
                        if (++ls == NG) { ls = 0; lph ^= 1; }
                    } else if (!role || mbar_test(smem_u32(&sm.wq_full), 0)) {
                        early = false;
                        break;
                    }
                    if (++n > (SPIN_LIMIT << 4)) __trap();
                }
            }
            while (inflight >= win) {
                mbar_wait(full0 + ls * 8, lph);
                inflight--;
                if (++ls == NG) { ls = 0; lph ^= 1; }
            }
            inflight++;
        };
        auto publish = [&](int p, int item) {
            const bool last = item >= NITEMS;
            sm.info[p] = last ? -1 : item;
            if (item >= 0) sm.progress = last ? 2 * NITEMS : item;
            mbar_arrive(smem_u32(&sm.tfull[p]));
        };
        auto copy = [&](uint32_t s, const unsigned char* src) {
            if (skip) { skip--; return; }
            throttle();
            mbar_expect_tx(full0 + s * 8, TILE_BYTES);
            bulk_load(ring + s * TILE_BYTES, src, TILE_BYTES, full0 + s * 8, pol);
        };
        int next = cta, pi = 0;
        uint32_t ph = 1;
        bool published = false;
        for (int n = 0;; n++) {
            const int item = next;
            const int pn = (pi + 1 == NSLOT) ? 0 : pi + 1;
            const uint32_t phn = (pi + 1 == NSLOT) ? ph ^ 1 : ph;
            if (!published) {
                mbar_wait(empty0 + (2 * pi) * 8, ph);
                publish(pi, item);
            }
            if (item == FFN_ITEM) {
                const uint32_t fk = full0 + (2 * pi) * 8, dst = ring + (2 * pi) * TILE_BYTES;
                throttle();
                mbar_expect_tx(fk, TILE_BYTES);
                if (n == NSTATIC) {
                    tensor_load_2d(dst, &tm_wg, fc * 16, 0, fk);
                    tensor_load_2d(dst + TILE_BYTES / 2, &tm_wg, fc * 16, 256, fk);
                    throttle();
                    mbar_expect_tx(fk + 8, TILE_BYTES);
                    tensor_load_2d(dst + TILE_BYTES, &tm_wu, fc * 16, 0, fk + 8);
                    tensor_load_2d(dst + TILE_BYTES + TILE_BYTES / 2, &tm_wu, fc * 16, 256, fk + 8);
                } else {
                    bulk_load(dst, wd + (size_t)fc * 16 * DM, TILE_BYTES, fk, pol);
                    inflight++;
                    mbar_arrive(fk + 8);
                    next = (int)(unsigned)v + NSTATIC * G;
                }
                published = false;
                pi = pn;
                ph = phn;
                continue;
            }
            if (item >= NITEMS) {
                mbar_arrive(full0 + (2 * pi) * 8);
                mbar_wait(empty0 + (2 * pn) * 8, phn);
                sm.info[pn] = -2;
                mbar_arrive(full0 + (2 * pn) * 8);
                if (role) {
                    const int pw = (pn + 1 == NSLOT) ? 0 : pn + 1;
                    const uint32_t phw = (pn + 1 == NSLOT) ? phn ^ 1 : phn;
                    mbar_wait(empty0 + (2 * pw) * 8, phw);
                    mbar_wait(empty0 + (2 * pw + 1) * 8, phw);
                    win = 1;
                    throttle();
                    mbar_expect_tx(smem_u32(&sm.wo_full), 2 * TILE_BYTES);
#pragma unroll 1
                    for (int i = 0; i < 8; i++)
                        bulk_load(ring + 2 * pw * TILE_BYTES + i * 4096, wo + (size_t)(((cta >> 5) + 4 * i) * DH + (cta & 31) * 4) * DM, 4096,
                                  smem_u32(&sm.wo_full), pol);
                }
                if (item == NITEMS + G - 1)
                    g_ticket = (unsigned long long)(sm.epoch + 1u) << 32;
                break;
            }
            if (n >= NSTATIC) v = atomicAdd(&g_ticket, 1ull);
            if (n == NSLOT - 1) mbar_wait(smem_u32(&sm.wq_done), 0);
            if (fc >= 0 && (n == NSTATIC + NSLOT || n == NSTATIC + NSLOT + 1)) mbar_wait(smem_u32(&sm.ffn_done[n - NSTATIC - NSLOT]), 0);
            copy(2 * pi, kb + (size_t)item * TILE_BYTES);
            mbar_wait(empty0 + (2 * pi + 1) * 8, ph);
            copy(2 * pi + 1, vb + (size_t)item * TILE_BYTES);
            if (n + 1 == NSTATIC) {
                mbar_wait(smem_u32(&sm.tag_ready), 0);
                v = sm.ticket0;
            }
            next = (n + 1 < NSTATIC) ? item + G : (n + 1 == NSTATIC && fc >= 0) ? FFN_ITEM : (int)(unsigned)v + NSTATIC * G;
            published = mbar_test(empty0 + (2 * pn) * 8, phn);
            if (published) publish(pn, next);
            pi = pn;
            ph = phn;
        }
    } else {
        if (lane == 0) {
            sm.epoch = (unsigned)(v >> 32);
            sm.tag = (unsigned)(v >> 32) % 65535u + 1u;
            sm.ticket0 = (unsigned)v;
            mbar_arrive(smem_u32(&sm.tag_ready));
        }
        mbar_wait(smem_u32(&sm.tag_ready), 0);
        const uint32_t tag = sm.tag;
        int pi = 0;
        uint32_t ph = 0;
        for (;;) {
            mbar_wait(smem_u32(&sm.tfull[pi]), ph);
            const int item = *reinterpret_cast<volatile int*>(&sm.info[pi]);
            if (item == FFN_ITEM) {
                if (lane == 0) mbar_arrive(smem_u32(&sm.qfull[pi]));
                if (++pi == NSLOT) { pi = 0; ph ^= 1; }
                continue;
            }
            if (item < 0) break;
            const uint4* src = &g_q[(item / TPB) * 32 + lane];
            uint4 r;
            unsigned n = 0;
            for (;;) {
                r = ld_ll64x2(src);
                if (r.y == tag && r.w == tag) break;
                __nanosleep(100);
                if (++n > SPIN_LIMIT) __trap();
            }
            *reinterpret_cast<uint2*>(&sm.qs[pi][lane * 2]) = make_uint2(r.x, r.z);
            __syncwarp();
            if (lane == 0) mbar_arrive(smem_u32(&sm.qfull[pi]));
            if (++pi == NSLOT) { pi = 0; ph ^= 1; }
        }
    }
}

}

extern "C" void kernel_launch(void* const* d_in, const int* in_sizes, int n_in, void* d_out, int out_size) {
    (void)in_sizes; (void)n_in; (void)out_size;
    typedef CUresult (*EncodeFn)(CUtensorMap*, CUtensorMapDataType, cuuint32_t, void*, const cuuint64_t*, const cuuint64_t*,
                                 const cuuint32_t*, const cuuint32_t*, CUtensorMapInterleave, CUtensorMapSwizzle,
                                 CUtensorMapL2promotion, CUtensorMapFloatOOBfill);
    static int grid = 0;
    static EncodeFn encode = nullptr;
    if (grid == 0) {
        int dev = 0, sms = 0;
        cudaGetDevice(&dev);
        cudaDeviceGetAttribute(&sms, cudaDevAttrMultiProcessorCount, dev);
        cudaFuncSetAttribute(fused_decode_kernel, cudaFuncAttributeMaxDynamicSharedMemorySize, (int)sizeof(Smem));
        grid = sms < NROLE ? NROLE : (sms > 160 ? 160 : sms);
        void* fn = nullptr;
        cudaDriverEntryPointQueryResult qr;
        cudaGetDriverEntryPoint("cuTensorMapEncodeTiled", &fn, cudaEnableDefault, &qr);
        encode = (EncodeFn)fn;
    }
    auto make_map = [&](void* base, int ncols, int box_cols) {
        CUtensorMap tm;
        const cuuint64_t dims[2] = {(cuuint64_t)ncols, (cuuint64_t)DM};
        const cuuint64_t strides[1] = {(cuuint64_t)ncols * 2};
        const cuuint32_t box[2] = {(cuuint32_t)box_cols, 256}, estr[2] = {1, 1};
        encode(&tm, CU_TENSOR_MAP_DATA_TYPE_BFLOAT16, 2, base, dims, strides, box, estr, CU_TENSOR_MAP_INTERLEAVE_NONE,
               CU_TENSOR_MAP_SWIZZLE_NONE, CU_TENSOR_MAP_L2_PROMOTION_L2_128B, CU_TENSOR_MAP_FLOAT_OOB_FILL_NONE);
        return tm;
    };
    const CUtensorMap tm_wq = make_map(d_in[3], NH * DH, 32), tm_wg = make_map(d_in[6], FF, 16), tm_wu = make_map(d_in[7], FF, 16);
    fused_decode_kernel<<<grid, NTHREADS, sizeof(Smem)>>>(
        tm_wq, tm_wg, tm_wu, (const __nv_bfloat16*)d_in[0], (const __nv_bfloat16*)d_in[1], (const __nv_bfloat16*)d_in[2],
        (const __nv_bfloat16*)d_in[4], (const __nv_bfloat16*)d_in[8], (__nv_bfloat16*)d_out);
}
```
